```python
import torch

def _softmax(x, axis=-1):
    return torch.softmax(x, dim=axis)
def _gelu(x):
    return torch.nn.functional.gelu(x, approximate="tanh")
def _silu(x):
    return torch.nn.functional.silu(x)
def _sigmoid(x):
    return torch.sigmoid(x)
def _layernorm(x, axis=-1, eps=1e-5):
    m = x.mean(dim=axis, keepdim=True)
    v = x.var(dim=axis, keepdim=True, unbiased=False)
    return (x - m) / torch.sqrt(v + eps)
def _scatter_add(tgt, idx, src, axis=0):
    return tgt.clone().index_add_(axis, idx, src)
def _segment_sum(src, seg, n):
    out = torch.zeros((n,) + src.shape[1:], dtype=src.dtype)
    return out.index_add_(0, seg, src)
def _pad(x, pw):
    flat = tuple(v for pair in reversed(pw) for v in pair)
    return torch.nn.functional.pad(x, flat)

kernel_name = 'concat_heads__gqa_block_cached__mha_block_cached__decode'

def setup_inputs():

    _w = (lambda a: (lambda t: t.to(torch.bfloat16) if t.is_floating_point() else t)(torch.as_tensor(a)))
    def _A_setup():
        B, Sq, D = 1, 1, 448
        Hq, Hkv, Sk, Dh = 16, 8, 32768, 256
        assert Hq % Hkv == 0, (Hq, Hkv)
        return {
            "x": _w((lambda *s: torch.randn(*s, dtype=torch.bfloat16) * 0.8)(B, Sq, D)),
            "k_cache": _w((lambda *s: torch.randn(*s, dtype=torch.bfloat16) * 1.6)(B, Hkv, Sk, Dh)),
            "v_cache": _w((lambda *s: torch.randn(*s, dtype=torch.bfloat16) * 0.2)(B, Hkv, Sk, Dh)),
            "wq": _w((lambda *s: torch.randn(*s, dtype=torch.bfloat16) * 1.6)(D, Hq * Dh) * (D ** -0.5)),
            "wo": _w((lambda *s: torch.randn(*s, dtype=torch.bfloat16) * 0.2)(Hq * Dh, D) * ((Hq * Dh) ** -0.5)),
        }
    _A_in = _A_setup()

    def _B_setup():
        B, Sq, D = 1, 1, 448
        H, Sk, Dh = 16, 32768, 256
        return {
            "x": _w((lambda *s: torch.randn(*s, dtype=torch.bfloat16) * 0.8)(B, Sq, D)),
            "k_cache": _w((lambda *s: torch.randn(*s, dtype=torch.bfloat16) * 1.6)(B, H, Sk, Dh)),
            "v_cache": _w((lambda *s: torch.randn(*s, dtype=torch.bfloat16) * 0.2)(B, H, Sk, Dh)),
            "wq": _w((lambda *s: torch.randn(*s, dtype=torch.bfloat16) * 1.6)(D, H * Dh) * (D ** -0.5)),
            "wo": _w((lambda *s: torch.randn(*s, dtype=torch.bfloat16) * 0.2)(H * Dh, D) * ((H * Dh) ** -0.5)),
        }
    _B_in = _B_setup()

    return {
        "A_x": _A_in["x"],
        "A_k_cache": _A_in["k_cache"],
        "A_v_cache": _A_in["v_cache"],
        "A_wq": _A_in["wq"],
        "A_wo": _A_in["wo"],
        "B_x": _B_in["x"],
        "B_k_cache": _B_in["k_cache"],
        "B_v_cache": _B_in["v_cache"],
        "B_wq": _B_in["wq"],
        "B_wo": _B_in["wo"],
    }

def reference(A_x, A_k_cache, A_v_cache, A_wq, A_wo, B_x, B_k_cache, B_v_cache, B_wq, B_wo):
    def _A_ref(x, k_cache, v_cache, wq, wo):
        B, Sq, D = x.shape
        Hq, Dh = 16, 256
        Hkv = k_cache.shape[1]
        rep = Hq // Hkv
        q = (lambda x, *d: x.permute(*d))((x @ wq).reshape(B, Sq, Hq, Dh), 0, 2, 1, 3)
        k = (lambda x, n, axis: torch.repeat_interleave(x, n, dim=axis))(k_cache, rep, axis=1)
        v = (lambda x, n, axis: torch.repeat_interleave(x, n, dim=axis))(v_cache, rep, axis=1)
        scores = torch.einsum("bhqd,bhkd->bhqk", q, k) * (Dh ** -0.5)
        p = _softmax(scores, axis=-1)
        o = torch.einsum("bhqk,bhkd->bhqd", p, v)
        return (lambda x, *d: x.permute(*d))(o, 0, 2, 1, 3).reshape(B, Sq, Hq * Dh) @ wo

    def _B_ref(x, k_cache, v_cache, wq, wo):
        B, Sq, D = x.shape
        H, Dh = 16, 256
        q = (lambda x, *d: x.permute(*d))((x @ wq).reshape(B, Sq, H, Dh), 0, 2, 1, 3)
        scores = torch.einsum("bhqd,bhkd->bhqk", q, k_cache) * (Dh ** -0.5)
        p = _softmax(scores, axis=-1)
        o = torch.einsum("bhqk,bhkd->bhqd", p, v_cache)
        return (lambda x, *d: x.permute(*d))(o, 0, 2, 1, 3).reshape(B, Sq, H * Dh) @ wo

    a = _A_ref(A_x, A_k_cache, A_v_cache, A_wq, A_wo)
    b = _B_ref(B_x, B_k_cache, B_v_cache, B_wq, B_wo)
    return torch.concatenate([a, b], axis=-1)
```

```cpp
#include <cuda_runtime.h>
#include <cuda_bf16.h>
#include <stdint.h>

namespace {

constexpr int kD            = 448;
constexpr int kDh           = 256;
constexpr int kSk           = 32768;
constexpr int kQH           = 16;
constexpr int kKvhA         = 8;
constexpr int kKvhB         = 16;
constexpr int kHD           = kQH * kDh;

constexpr int kTileRows     = 32;
constexpr int kTileBytes    = kTileRows * kDh * 2;
constexpr int kTilesPerHead = kSk / kTileRows;
constexpr int kTilesA       = kKvhA * kTilesPerHead;
constexpr int kTilesB       = kKvhB * kTilesPerHead;
constexpr int kTiles        = kTilesA + kTilesB;
constexpr int kStages       = 6;
constexpr int kNCW          = 8;
constexpr int kNCT          = kNCW * 32;
constexpr int kThreads      = kNCT + 32;
constexpr int kMaxGrid      = 160;
constexpr int kNumGridBars  = 3;
constexpr int kMaxSliceRows = 64;

constexpr float kLog2e = 1.4426950408889634f;

struct Params {
    const __nv_bfloat16 *xA, *kA, *vA, *wqA, *woA;
    const __nv_bfloat16 *xB, *kB, *vB, *wqB, *woB;
    __nv_bfloat16* out;
    int mode;
    int maxTiles;
    int sliceRowsMax;
};

__device__ __nv_bfloat16 g_q[2 * kHD];
__device__ float2 g_ml[2 * kQH * kMaxGrid];
__device__ float  g_po[2 * kQH * kMaxGrid * kDh];
__device__ float  g_outp[kMaxGrid * kD];
__device__ unsigned long long g_bar;

__device__ __forceinline__ uint32_t smem_u32(const void* p) { return (uint32_t)__cvta_generic_to_shared(p); }
__device__ __forceinline__ void mbar_init(uint32_t bar, uint32_t cnt) {
    asm volatile("mbarrier.init.shared::cta.b64 [%0], %1;" :: "r"(bar), "r"(cnt));
}
__device__ __forceinline__ void mbar_expect_tx(uint32_t bar, uint32_t bytes) {
    asm volatile("mbarrier.arrive.expect_tx.shared::cta.b64 _, [%0], %1;" :: "r"(bar), "r"(bytes) : "memory");
}
__device__ __forceinline__ void mbar_arrive(uint32_t bar) {
    asm volatile("mbarrier.arrive.shared::cta.b64 _, [%0];" :: "r"(bar) : "memory");
}
__device__ __forceinline__ bool mbar_try_wait(uint32_t bar, uint32_t parity) {
    uint32_t ok;
    asm volatile("{\n.reg .pred p;\nmbarrier.try_wait.parity.shared::cta.b64 p, [%1], %2;\nselp.u32 %0, 1, 0, p;\n}"
                 : "=r"(ok) : "r"(bar), "r"(parity) : "memory");
    return ok != 0;
}
__device__ __forceinline__ void mbar_wait(uint32_t bar, uint32_t parity) {
    uint32_t spins = 0;
    while (!mbar_try_wait(bar, parity)) {
        if (++spins > (1u << 24)) __trap();
    }
}
__device__ __forceinline__ void bulk_g2s(uint32_t dst, const void* src, uint32_t bytes, uint32_t bar) {
    asm volatile("cp.async.bulk.shared::cluster.global.mbarrier::complete_tx::bytes [%0], [%1], %2, [%3];"
                 :: "r"(dst), "l"(src), "r"(bytes), "r"(bar) : "memory");
}
__device__ __forceinline__ void consumer_sync() { asm volatile("bar.sync 1, %0;" :: "n"(kNCT) : "memory"); }
__device__ __forceinline__ float bf16lo(uint32_t w) { return __uint_as_float(w << 16); }
__device__ __forceinline__ float bf16hi(uint32_t w) { return __uint_as_float(w & 0xffff0000u); }
__device__ __forceinline__ float bf16round(float x) { return __bfloat162float(__float2bfloat16_rn(x)); }
__device__ __forceinline__ float ex2(float x) { float y; asm("ex2.approx.ftz.f32 %0, %1;" : "=f"(y) : "f"(x)); return y; }

__device__ __forceinline__ void grid_arrive_wait(unsigned long long target) {
    __threadfence();
    atomicAdd(&g_bar, 1ULL);
    unsigned long long v;
    uint32_t spins = 0;
    do {
        asm volatile("ld.acquire.gpu.global.u64 %0, [%1];" : "=l"(v) : "l"(&g_bar) : "memory");
        if (++spins > (1u << 24)) __trap();
    } while (v < target);
}

struct SmemLayout {
    int ring, wo, scores, q, misc, total;
};
__host__ __device__ inline SmemLayout make_layout(int maxTiles, int sliceRowsMax) {
    SmemLayout L;
    L.ring   = 0;
    L.wo     = L.ring + kStages * kTileBytes;
    L.scores = L.wo + ((sliceRowsMax * kD * 2 + 127) / 128) * 128;
    L.q      = L.scores + maxTiles * 64 * 4;
    L.misc   = L.q + 2 * kHD * 2;
    L.total  = L.misc + 4096;
    return L;
}
struct Misc {
    uint64_t full[kStages];
    uint64_t empty[kStages];
    uint64_t wobar;
    unsigned long long bar_base;
    float  wmax[2 * kQH][kNCW];
    float2 ml[2 * kQH];
    float  lbuf[kNCW * 2];
    float  wts[2][kMaxGrid];
    float  linv[2];
    float  red[4][kMaxSliceRows];
    float  os[kMaxSliceRows];
};
static_assert(sizeof(Misc) <= 4096, "misc too big");

struct Ring { int stage; uint32_t phase; };
__device__ __forceinline__ void ring_advance(Ring& r) { if (++r.stage == kStages) { r.stage = 0; r.phase ^= 1; } }

__device__ __forceinline__ float reduce4(float a0, float a1, float a2, float a3, int lane) {
    const bool hi16 = (lane & 16) != 0;
    float s0 = hi16 ? a0 : a2, k0 = hi16 ? a2 : a0;
    float s1 = hi16 ? a1 : a3, k1 = hi16 ? a3 : a1;
    k0 += __shfl_xor_sync(0xffffffffu, s0, 16);
    k1 += __shfl_xor_sync(0xffffffffu, s1, 16);
    const bool hi8 = (lane & 8) != 0;
    float s = hi8 ? k0 : k1, k = hi8 ? k1 : k0;
    k += __shfl_xor_sync(0xffffffffu, s, 8);
    k += __shfl_xor_sync(0xffffffffu, k, 4);
    k += __shfl_xor_sync(0xffffffffu, k, 2);
    k += __shfl_xor_sync(0xffffffffu, k, 1);
    return k;
}

template <int NH>
__device__ __forceinline__ void k_segment(int i0, int i1, int qh0, Ring& ring, char* smem_ring, float* sc,
                                          const __nv_bfloat16* qs, Misc* ms, int warp, int lane) {
    float q[NH][8];
#pragma unroll
    for (int h = 0; h < NH; ++h) {
        const uint4 qv = *reinterpret_cast<const uint4*>(qs + (qh0 + h) * kDh + lane * 8);
        q[h][0] = bf16lo(qv.x); q[h][1] = bf16hi(qv.x);
        q[h][2] = bf16lo(qv.y); q[h][3] = bf16hi(qv.y);
        q[h][4] = bf16lo(qv.z); q[h][5] = bf16hi(qv.z);
        q[h][6] = bf16lo(qv.w); q[h][7] = bf16hi(qv.w);
    }
    float mx[NH];
#pragma unroll
    for (int h = 0; h < NH; ++h) mx[h] = -INFINITY;
    const int row = ((lane >> 4) << 1) | ((lane >> 3) & 1);

    for (int i = i0; i < i1; ++i) {
        mbar_wait(smem_u32(&ms->full[ring.stage]), ring.phase);
        const uint4* kt = reinterpret_cast<const uint4*>(smem_ring + ring.stage * kTileBytes) + (warp * 4) * 32 + lane;
        uint4 kv[4];
#pragma unroll
        for (int j = 0; j < 4; ++j) kv[j] = kt[j * 32];
        float acc[NH][4];
#pragma unroll
        for (int h = 0; h < NH; ++h)
#pragma unroll
            for (int j = 0; j < 4; ++j) acc[h][j] = 0.f;
#pragma unroll
        for (int j = 0; j < 4; ++j) {
            const uint32_t w[4] = {kv[j].x, kv[j].y, kv[j].z, kv[j].w};
#pragma unroll
            for (int e = 0; e < 4; ++e) {
                const float lo = bf16lo(w[e]), hi = bf16hi(w[e]);
#pragma unroll
                for (int h = 0; h < NH; ++h) {
                    acc[h][j] = fmaf(q[h][2 * e], lo, acc[h][j]);
                    acc[h][j] = fmaf(q[h][2 * e + 1], hi, acc[h][j]);
                }
            }
        }
        __syncwarp();
        if (lane == 0) mbar_arrive(smem_u32(&ms->empty[ring.stage]));
        ring_advance(ring);
#pragma unroll
        for (int h = 0; h < NH; ++h) {
            const float dot = reduce4(acc[h][0], acc[h][1], acc[h][2], acc[h][3], lane);
            const float s = bf16round(bf16round(dot) * 0.0625f);
            mx[h] = fmaxf(mx[h], s);
            if ((lane & 7) == 0) sc[i * 64 + h * 32 + warp * 4 + row] = s;
        }
    }
#pragma unroll
    for (int h = 0; h < NH; ++h) {
        float m = mx[h];
        m = fmaxf(m, __shfl_xor_sync(0xffffffffu, m, 16));
        m = fmaxf(m, __shfl_xor_sync(0xffffffffu, m, 8));
        if (lane == 0) ms->wmax[qh0 + h][warp] = m;
    }
}

template <int NH>
__device__ __forceinline__ void v_segment(int i0, int i1, int qh0, Ring& ring, char* smem_ring, const float* sc,
                                          float* mbuf, Misc* ms, int warp, int lane, int cta, int G) {
    float mref[NH], ml2[NH];
#pragma unroll
    for (int h = 0; h < NH; ++h) {
        float m = -INFINITY;
#pragma unroll
        for (int w = 0; w < kNCW; ++w) m = fmaxf(m, ms->wmax[qh0 + h][w]);
        mref[h] = m;
        ml2[h] = m * kLog2e;
    }
    float acc[NH][8], l[NH];
#pragma unroll
    for (int h = 0; h < NH; ++h) {
        l[h] = 0.f;
#pragma unroll
        for (int d = 0; d < 8; ++d) acc[h][d] = 0.f;
    }
    for (int i = i0; i < i1; ++i) {
        mbar_wait(smem_u32(&ms->full[ring.stage]), ring.phase);
        const uint4* vt = reinterpret_cast<const uint4*>(smem_ring + ring.stage * kTileBytes) + (warp * 4) * 32 + lane;
        uint4 vv[4];
#pragma unroll
        for (int j = 0; j < 4; ++j) vv[j] = vt[j * 32];
        float p[NH][4];
#pragma unroll
        for (int h = 0; h < NH; ++h) {
            const float4 s4 = *reinterpret_cast<const float4*>(sc + i * 64 + h * 32 + warp * 4);
            p[h][0] = ex2(fmaf(s4.x, kLog2e, -ml2[h]));
            p[h][1] = ex2(fmaf(s4.y, kLog2e, -ml2[h]));
            p[h][2] = ex2(fmaf(s4.z, kLog2e, -ml2[h]));
            p[h][3] = ex2(fmaf(s4.w, kLog2e, -ml2[h]));
            l[h] += (p[h][0] + p[h][1]) + (p[h][2] + p[h][3]);
        }
#pragma unroll
        for (int j = 0; j < 4; ++j) {
            const uint32_t w[4] = {vv[j].x, vv[j].y, vv[j].z, vv[j].w};
#pragma unroll
            for (int e = 0; e < 4; ++e) {
                const float lo = bf16lo(w[e]), hi = bf16hi(w[e]);
#pragma unroll
                for (int h = 0; h < NH; ++h) {
                    acc[h][2 * e]     = fmaf(p[h][j], lo, acc[h][2 * e]);
                    acc[h][2 * e + 1] = fmaf(p[h][j], hi, acc[h][2 * e + 1]);
                }
            }
        }
        __syncwarp();
        if (lane == 0) mbar_arrive(smem_u32(&ms->empty[ring.stage]));
        ring_advance(ring);
    }
    const int t = warp * 32 + lane;
#pragma unroll
    for (int h = 0; h < NH; ++h) {
        float4* mb = reinterpret_cast<float4*>(mbuf + (warp * 2 + h) * kDh + lane * 8);
        mb[0] = make_float4(acc[h][0], acc[h][1], acc[h][2], acc[h][3]);
        mb[1] = make_float4(acc[h][4], acc[h][5], acc[h][6], acc[h][7]);
        if (lane == 0) ms->lbuf[warp * 2 + h] = l[h];
    }
    consumer_sync();
#pragma unroll
    for (int h = 0; h < NH; ++h) {
        float s = 0.f;
#pragma unroll
        for (int w = 0; w < kNCW; ++w) s += mbuf[(w * 2 + h) * kDh + t];
        g_po[((size_t)(qh0 + h) * G + cta) * kDh + t] = s;
        if (t == h) {
            float ls = 0.f;
#pragma unroll
            for (int w = 0; w < kNCW; ++w) ls += ms->lbuf[w * 2 + h];
            ms->ml[qh0 + h] = make_float2(mref[h], ls);
        }
    }
    consumer_sync();
}

__global__ void __launch_bounds__(kThreads, 1)
attn_decode_kernel(const Params P) {
    extern __shared__ __align__(1024) char smem[];
    const SmemLayout L = make_layout(P.maxTiles, P.sliceRowsMax);
    char*  smem_ring = smem + L.ring;
    char*  wo_s      = smem + L.wo;
    float* sc        = reinterpret_cast<float*>(smem + L.scores);
    __nv_bfloat16* qs = reinterpret_cast<__nv_bfloat16*>(smem + L.q);
    float* mbuf      = reinterpret_cast<float*>(smem + L.q);
    Misc*  ms        = reinterpret_cast<Misc*>(smem + L.misc);

    const int tid = threadIdx.x, warp = tid >> 5, lane = tid & 31;
    const int G = gridDim.x, c = blockIdx.x;

    int start, stride, cnt;
    if (P.mode == 0) {
        start  = (int)((long long)kTiles * c / G);
        cnt    = (int)((long long)kTiles * (c + 1) / G) - start;
        stride = 1;
    } else {
        start  = c;
        stride = G;
        cnt    = (kTiles - c + G - 1) / G;
    }

    const int half = G >> 1;
    const int part_t = (c < 2 * half) ? (c / half) : -1;
    const int sidx = (part_t >= 0) ? (c - part_t * half) : 0;
    const int r0 = (int)((long long)kHD * sidx / half);
    const int r1 = (int)((long long)kHD * (sidx + 1) / half);
    const int nr = (part_t >= 0) ? (r1 - r0) : 0;

    if (tid == 0) {
        for (int s = 0; s < kStages; ++s) {
            mbar_init(smem_u32(&ms->full[s]), 1);
            mbar_init(smem_u32(&ms->empty[s]), kNCW);
        }
        mbar_init(smem_u32(&ms->wobar), 1);
        asm volatile("fence.mbarrier_init.release.cluster;" ::: "memory");
        unsigned long long v;
        asm volatile("ld.acquire.gpu.global.u64 %0, [%1];" : "=l"(v) : "l"(&g_bar) : "memory");
        const unsigned long long per = (unsigned long long)kNumGridBars * G;
        ms->bar_base = (v / per) * per;
    }
    for (int i = tid; i < 2 * kQH; i += kThreads) ms->ml[i] = make_float2(-INFINITY, 0.f);
    __syncthreads();

    if (warp == kNCW) {
        if (lane == 0) {
            if (nr > 0) {
                const __nv_bfloat16* wo = (part_t == 0 ? P.woA : P.woB) + (size_t)r0 * kD;
                mbar_expect_tx(smem_u32(&ms->wobar), (uint32_t)(nr * kD * 2));
                bulk_g2s(smem_u32(wo_s), wo, (uint32_t)(nr * kD * 2), smem_u32(&ms->wobar));
            }
            Ring r{0, 1};
            for (int ph = 0; ph < 2; ++ph) {
                const char* baseA = reinterpret_cast<const char*>(ph == 0 ? P.kA : P.vA);
                const char* baseB = reinterpret_cast<const char*>(ph == 0 ? P.kB : P.vB);
                for (int i = 0; i < cnt; ++i) {
                    const int g = start + i * stride;
                    const char* src = (g < kTilesA) ? baseA + (size_t)g * kTileBytes
                                                    : baseB + (size_t)(g - kTilesA) * kTileBytes;
                    mbar_wait(smem_u32(&ms->empty[r.stage]), r.phase);
                    mbar_expect_tx(smem_u32(&ms->full[r.stage]), kTileBytes);
                    bulk_g2s(smem_u32(smem_ring + r.stage * kTileBytes), src, kTileBytes, smem_u32(&ms->full[r.stage]));
                    ring_advance(r);
                }
            }
        }
        return;
    }

    const unsigned long long bar_base = ms->bar_base;

    {
        float* qred = reinterpret_cast<float*>(smem_ring + (kStages - 1) * kTileBytes);
        (void)qred;
    }
    {
        float* qred = sc;
        for (int blk = c; blk < 2 * kHD / 64; blk += G) {
            const int part = blk / (kHD / 64);
            const int n0 = (blk % (kHD / 64)) * 64;
            const __nv_bfloat16* x  = part ? P.xB : P.xA;
            const __nv_bfloat16* wq = part ? P.wqB : P.wqA;
            const int chunk = tid & 7, krow = tid >> 3;
            float a[8];
#pragma unroll
            for (int e = 0; e < 8; ++e) a[e] = 0.f;
#pragma unroll
            for (int it = 0; it < kD / 32; ++it) {
                const int k = krow + it * 32;
                const uint4 w = __ldg(reinterpret_cast<const uint4*>(wq + (size_t)k * kHD + n0 + chunk * 8));
                const float xv = __bfloat162float(x[k]);
                a[0] = fmaf(xv, bf16lo(w.x), a[0]); a[1] = fmaf(xv, bf16hi(w.x), a[1]);
                a[2] = fmaf(xv, bf16lo(w.y), a[2]); a[3] = fmaf(xv, bf16hi(w.y), a[3]);
                a[4] = fmaf(xv, bf16lo(w.z), a[4]); a[5] = fmaf(xv, bf16hi(w.z), a[5]);
                a[6] = fmaf(xv, bf16lo(w.w), a[6]); a[7] = fmaf(xv, bf16hi(w.w), a[7]);
            }
#pragma unroll
            for (int e = 0; e < 8; ++e) {
                a[e] += __shfl_xor_sync(0xffffffffu, a[e], 8);
                a[e] += __shfl_xor_sync(0xffffffffu, a[e], 16);
            }
            if (lane < 8) {
#pragma unroll
                for (int e = 0; e < 8; ++e) qred[warp * 64 + lane * 8 + e] = a[e];
            }
            consumer_sync();
            if (tid < 64) {
                float s = 0.f;
#pragma unroll
                for (int w = 0; w < kNCW; ++w) s += qred[w * 64 + tid];
                g_q[part * kHD + n0 + tid] = __float2bfloat16_rn(s);
            }
            consumer_sync();
        }
    }
    if (tid == 0) grid_arrive_wait(bar_base + 1ULL * G);
    consumer_sync();
    for (int i = tid; i < 2 * kHD / 8; i += kNCT)
        reinterpret_cast<uint4*>(qs)[i] = __ldcg(reinterpret_cast<const uint4*>(g_q) + i);
    for (int i = tid; i < 2 * kQH * kNCW; i += kNCT) (&ms->wmax[0][0])[i] = -INFINITY;
    consumer_sync();

    Ring ring{0, 0};
    for (int i = 0; i < cnt;) {
        const int g = start + i * stride;
        const bool pb = g >= kTilesA;
        const int gl = pb ? g - kTilesA : g;
        const int kvh = gl / kTilesPerHead;
        const int gend = (pb ? kTilesA : 0) + (kvh + 1) * kTilesPerHead;
        int iend = (gend - start + stride - 1) / stride;
        if (iend > cnt) iend = cnt;
        if (!pb) k_segment<2>(i, iend, kvh * 2, ring, smem_ring, sc, qs, ms, warp, lane);
        else     k_segment<1>(i, iend, kQH + kvh, ring, smem_ring, sc, qs, ms, warp, lane);
        i = iend;
    }
    consumer_sync();
    for (int i = 0; i < cnt;) {
        const int g = start + i * stride;
        const bool pb = g >= kTilesA;
        const int gl = pb ? g - kTilesA : g;
        const int kvh = gl / kTilesPerHead;
        const int gend = (pb ? kTilesA : 0) + (kvh + 1) * kTilesPerHead;
        int iend = (gend - start + stride - 1) / stride;
        if (iend > cnt) iend = cnt;
        if (!pb) v_segment<2>(i, iend, kvh * 2, ring, smem_ring, sc, mbuf, ms, warp, lane, c, G);
        else     v_segment<1>(i, iend, kQH + kvh, ring, smem_ring, sc, mbuf, ms, warp, lane, c, G);
        i = iend;
    }
    if (tid < 2 * kQH) g_ml[tid * G + c] = ms->ml[tid];
    consumer_sync();
    if (tid == 0) grid_arrive_wait(bar_base + 2ULL * G);
    consumer_sync();

    if (nr > 0) {
        const int hA = part_t * kQH + r0 / kDh;
        const int hB = part_t * kQH + (r1 - 1) / kDh;
        if (warp < 2 && hA + warp <= hB) {
            const int head = hA + warp;
            float m = -INFINITY;
            for (int cc = lane; cc < G; cc += 32) m = fmaxf(m, __ldcg(&g_ml[head * G + cc]).x);
#pragma unroll
            for (int o = 16; o > 0; o >>= 1) m = fmaxf(m, __shfl_xor_sync(0xffffffffu, m, o));
            float ls = 0.f;
            for (int cc = lane; cc < G; cc += 32) {
                const float2 v = __ldcg(&g_ml[head * G + cc]);
                const float w = (v.y > 0.f) ? ex2((v.x - m) * kLog2e) : 0.f;
                ms->wts[warp][cc] = w;
                ls = fmaf(w, v.y, ls);
            }
#pragma unroll
            for (int o = 16; o > 0; o >>= 1) ls += __shfl_xor_sync(0xffffffffu, ls, o);
            if (lane == 0) ms->linv[warp] = 1.0f / ls;
        }
        consumer_sync();
        {
            const int row = tid & 63, grp = tid >> 6;
            float s = 0.f;
            if (row < nr) {
                const int i = r0 + row;
                const int head = part_t * kQH + i / kDh, d = i % kDh, hs = head - hA;
                for (int cc = grp; cc < G; cc += 4) {
                    const float w = ms->wts[hs][cc];
                    if (w != 0.f) s = fmaf(w, __ldcg(&g_po[((size_t)head * G + cc) * kDh + d]), s);
                }
            }
            ms->red[grp][row] = s;
        }
        consumer_sync();
        if (tid < nr) {
            const int i = r0 + tid;
            const int hs = part_t * kQH + i / kDh - hA;
            const float tot = (ms->red[0][tid] + ms->red[1][tid]) + (ms->red[2][tid] + ms->red[3][tid]);
            ms->os[tid] = bf16round(tot * ms->linv[hs]);
        }
        consumer_sync();
        mbar_wait(smem_u32(&ms->wobar), 0);
        if (tid < kD / 2) {
            const uint32_t* w2 = reinterpret_cast<const uint32_t*>(wo_s) + tid;
            float a0 = 0.f, a1 = 0.f;
            for (int r = 0; r < nr; ++r) {
                const uint32_t w = w2[r * (kD / 2)];
                const float o = ms->os[r];
                a0 = fmaf(o, bf16lo(w), a0);
                a1 = fmaf(o, bf16hi(w), a1);
            }
            *reinterpret_cast<float2*>(&g_outp[c * kD + 2 * tid]) = make_float2(a0, a1);
        }
    }
    consumer_sync();
    if (tid == 0) grid_arrive_wait(bar_base + 3ULL * G);
    consumer_sync();

    for (int blk = c; blk < 2 * kD / 64; blk += G) {
        const int j = blk * 64 + (tid & 63), grp = tid >> 6;
        const int pj = j / kD, col = j - pj * kD;
        float s = 0.f;
        for (int cc = grp; cc < half; cc += 4) s += __ldcg(&g_outp[(pj * half + cc) * kD + col]);
        ms->red[grp][tid & 63] = s;
        consumer_sync();
        if (tid < 64) {
            const float tot = (ms->red[0][tid] + ms->red[1][tid]) + (ms->red[2][tid] + ms->red[3][tid]);
            P.out[blk * 64 + tid] = __float2bfloat16_rn(tot);
        }
        consumer_sync();
    }
}

}

#define ATTN_MODE 1

extern "C" void kernel_launch(void* const* d_in, const int* in_sizes, int n_in,
                              void* d_out, int out_size) {
    (void)in_sizes; (void)n_in; (void)out_size;
    Params P;
    P.xA  = (const __nv_bfloat16*)d_in[0];
    P.kA  = (const __nv_bfloat16*)d_in[1];
    P.vA  = (const __nv_bfloat16*)d_in[2];
    P.wqA = (const __nv_bfloat16*)d_in[3];
    P.woA = (const __nv_bfloat16*)d_in[4];
    P.xB  = (const __nv_bfloat16*)d_in[5];
    P.kB  = (const __nv_bfloat16*)d_in[6];
    P.vB  = (const __nv_bfloat16*)d_in[7];
    P.wqB = (const __nv_bfloat16*)d_in[8];
    P.woB = (const __nv_bfloat16*)d_in[9];
    P.out = (__nv_bfloat16*)d_out;
    P.mode = ATTN_MODE;

    int dev = 0, sms = 0;
    cudaGetDevice(&dev);
    cudaDeviceGetAttribute(&sms, cudaDevAttrMultiProcessorCount, dev);
    int G = sms < kMaxGrid ? sms : kMaxGrid;
    if (G & 1) G -= 1;
    P.maxTiles = (kTiles + G - 1) / G;
    P.sliceRowsMax = (kHD + (G / 2) - 1) / (G / 2);
    const SmemLayout L = make_layout(P.maxTiles, P.sliceRowsMax);
    cudaFuncSetAttribute(attn_decode_kernel, cudaFuncAttributeMaxDynamicSharedMemorySize, L.total);
    attn_decode_kernel<<<G, kThreads, L.total>>>(P);
}
```

```cpp
#include <cuda_runtime.h>
#include <cuda_bf16.h>
#include <stdint.h>

namespace {

constexpr int kD            = 448;
constexpr int kDh           = 256;
constexpr int kSk           = 32768;
constexpr int kQH           = 16;
constexpr int kKvhA         = 8;
constexpr int kKvhB         = 16;
constexpr int kHD           = kQH * kDh;

constexpr int kTileRows     = 32;
constexpr int kTileBytes    = kTileRows * kDh * 2;
constexpr int kTilesPerHead = kSk / kTileRows;
static_assert(kTilesPerHead == 1024, "tile -> head uses >> 10");
constexpr int kTilesA       = kKvhA * kTilesPerHead;
constexpr int kTilesB       = kKvhB * kTilesPerHead;
constexpr int kTiles        = kTilesA + kTilesB;
#define ATTN_STAGES 6
#define ATTN_BATCH 2
constexpr int kStages       = ATTN_STAGES;
constexpr int kBatch        = ATTN_BATCH;
constexpr int kNCW          = 8;
constexpr int kNCT          = kNCW * 32;
constexpr int kThreads      = kNCT + 32;
constexpr int kMaxGrid      = 160;
constexpr int kNumGridBars  = 4;
constexpr int kSliceRows    = 64;
constexpr int kNumSlices    = 2 * kHD / kSliceRows;
constexpr int kScoreElemsA  = kTilesA * 64;
constexpr int kScoreElems   = kScoreElemsA + kTilesB * 32;

constexpr float kLog2e = 1.4426950408889634f;

struct Params {
    const __nv_bfloat16 *xA, *kA, *vA, *wqA, *woA;
    const __nv_bfloat16 *xB, *kB, *vB, *wqB, *woB;
    __nv_bfloat16* out;
};

__device__ __nv_bfloat16 g_q[2 * kHD];
__device__ float  g_l[2 * kQH * kMaxGrid];
__device__ __nv_bfloat16 g_scores[kScoreElems];
__device__ unsigned int g_gmax[2 * kQH];
__device__ float  g_po[2 * kQH * kMaxGrid * kDh];
__device__ float  g_outp[kNumSlices * kD];
__device__ unsigned long long g_bar;
__device__ unsigned int g_tile_ctr[2];

#define STAMP(i) do { } while (0)

__device__ __forceinline__ uint32_t smem_u32(const void* p) { return (uint32_t)__cvta_generic_to_shared(p); }
__device__ __forceinline__ void mbar_init(uint32_t bar, uint32_t cnt) {
    asm volatile("mbarrier.init.shared::cta.b64 [%0], %1;" :: "r"(bar), "r"(cnt));
}
__device__ __forceinline__ void mbar_expect_tx(uint32_t bar, uint32_t bytes) {
    asm volatile("mbarrier.arrive.expect_tx.shared::cta.b64 _, [%0], %1;" :: "r"(bar), "r"(bytes) : "memory");
}
__device__ __forceinline__ void mbar_arrive(uint32_t bar) {
    asm volatile("mbarrier.arrive.shared::cta.b64 _, [%0];" :: "r"(bar) : "memory");
}
__device__ __forceinline__ bool mbar_try_wait(uint32_t bar, uint32_t parity) {
    uint32_t ok;
    asm volatile("{\n.reg .pred p;\nmbarrier.try_wait.parity.shared::cta.b64 p, [%1], %2;\nselp.u32 %0, 1, 0, p;\n}"
                 : "=r"(ok) : "r"(bar), "r"(parity) : "memory");
    return ok != 0;
}
__device__ __forceinline__ void mbar_wait(uint32_t bar, uint32_t parity) {
    uint32_t spins = 0;
    while (!mbar_try_wait(bar, parity)) {
        if (++spins > (1u << 24)) __trap();
    }
}
__device__ __forceinline__ void bulk_g2s(uint32_t dst, const void* src, uint32_t bytes, uint32_t bar) {
    asm volatile("cp.async.bulk.shared::cluster.global.mbarrier::complete_tx::bytes [%0], [%1], %2, [%3];"
                 :: "r"(dst), "l"(src), "r"(bytes), "r"(bar) : "memory");
}
__device__ __forceinline__ void bulk_g2s_stream(uint32_t dst, const void* src, uint32_t bytes, uint32_t bar, uint64_t pol) {
    asm volatile("cp.async.bulk.shared::cluster.global.mbarrier::complete_tx::bytes.L2::cache_hint [%0], [%1], %2, [%3], %4;"
                 :: "r"(dst), "l"(src), "r"(bytes), "r"(bar), "l"(pol) : "memory");
}
__device__ __forceinline__ void consumer_sync() { asm volatile("bar.sync 1, %0;" :: "n"(kNCT) : "memory"); }
__device__ __forceinline__ float bf16lo(uint32_t w) { return __uint_as_float(w << 16); }
__device__ __forceinline__ float bf16hi(uint32_t w) { return __uint_as_float(w & 0xffff0000u); }
__device__ __forceinline__ float bf16round(float x) { return __bfloat162float(__float2bfloat16_rn(x)); }
__device__ __forceinline__ float ex2(float x) { float y; asm("ex2.approx.ftz.f32 %0, %1;" : "=f"(y) : "f"(x)); return y; }
__device__ __forceinline__ int lds_i32(const int* p) {
    int v; asm volatile("ld.volatile.shared.s32 %0, [%1];" : "=r"(v) : "r"(smem_u32(p)) : "memory"); return v;
}

__device__ __forceinline__ unsigned enc_f(float f) { const unsigned b = __float_as_uint(f); return (b & 0x80000000u) ? ~b : (b | 0x80000000u); }
__device__ __forceinline__ float dec_f(unsigned u) { return __uint_as_float((u & 0x80000000u) ? (u & 0x7fffffffu) : ~u); }

__device__ __forceinline__ void grid_arrive_wait(unsigned long long target) {
    __threadfence();
    atomicAdd(&g_bar, 1ULL);
    unsigned long long v;
    uint32_t spins = 0;
    do {
        asm volatile("ld.acquire.gpu.global.u64 %0, [%1];" : "=l"(v) : "l"(&g_bar) : "memory");
        if (++spins > (1u << 24)) __trap();
    } while (v < target);
}

struct Misc {
    uint64_t full[kStages];
    uint64_t empty[kStages];
    uint64_t wobar;
    uint64_t qbar;
    uint64_t sbar;
    unsigned long long bar_base;
    int    slot_g[kStages];
    float  gmax2[2 * kQH];
    float  wmax[2 * kQH][kNCW];
    float  l[2 * kQH];
    float  lbuf[kNCW * 2];
    float  linv;
    alignas(16) float red[kNCW][kSliceRows];
    alignas(16) float os[kSliceRows];
};
constexpr int kStageBytes = kTileBytes + 128;
constexpr int kOffRing   = 0;
constexpr int kOffWo     = kOffRing + kStages * kStageBytes;
constexpr int kOffQ      = kOffWo + kSliceRows * kD * 2;
constexpr int kOffMisc   = kOffQ + 2 * kHD * 2;
constexpr int kSmemTotal = kOffMisc + ((int)sizeof(Misc) + 127) / 128 * 128;
static_assert(kSmemTotal <= 232448, "shared memory budget exceeded");

struct Ring { int stage; uint32_t phase; };
__device__ __forceinline__ void ring_advance(Ring& r) { if (++r.stage == kStages) { r.stage = 0; r.phase ^= 1; } }

__device__ __forceinline__ float reduce4(float a0, float a1, float a2, float a3, int lane) {
    const bool hi16 = (lane & 16) != 0;
    float s0 = hi16 ? a0 : a2, k0 = hi16 ? a2 : a0;
    float s1 = hi16 ? a1 : a3, k1 = hi16 ? a3 : a1;
    k0 += __shfl_xor_sync(0xffffffffu, s0, 16);
    k1 += __shfl_xor_sync(0xffffffffu, s1, 16);
    const bool hi8 = (lane & 8) != 0;
    float s = hi8 ? k0 : k1, k = hi8 ? k1 : k0;
    k += __shfl_xor_sync(0xffffffffu, s, 8);
    k += __shfl_xor_sync(0xffffffffu, k, 4);
    k += __shfl_xor_sync(0xffffffffu, k, 2);
    k += __shfl_xor_sync(0xffffffffu, k, 1);
    return k;
}

template <int NH>
__device__ __forceinline__ void k_run(int& g, Ring& ring, const char* smem_ring,
                                      const __nv_bfloat16* qs, Misc* ms, int warp, int lane) {
    const int tag = g >> 10;
    const int qh0 = (NH == 2) ? tag * 2 : kQH + (tag - kKvhA);
    float q[NH][8];
#pragma unroll
    for (int h = 0; h < NH; ++h) {
        const uint4 qv = *reinterpret_cast<const uint4*>(qs + (qh0 + h) * kDh + lane * 8);
        q[h][0] = bf16lo(qv.x); q[h][1] = bf16hi(qv.x);
        q[h][2] = bf16lo(qv.y); q[h][3] = bf16hi(qv.y);
        q[h][4] = bf16lo(qv.z); q[h][5] = bf16hi(qv.z);
        q[h][6] = bf16lo(qv.w); q[h][7] = bf16hi(qv.w);
    }
    float mx[NH];
#pragma unroll
    for (int h = 0; h < NH; ++h) mx[h] = -INFINITY;
    const int row = ((lane >> 4) << 1) | ((lane >> 3) & 1);

    do {
        const uint4* kt = reinterpret_cast<const uint4*>(smem_ring + ring.stage * kStageBytes) + (warp * 4) * 32 + lane;
        uint4 kv[4];
#pragma unroll
        for (int j = 0; j < 4; ++j) kv[j] = kt[j * 32];
        float acc[NH][4];
#pragma unroll
        for (int h = 0; h < NH; ++h)
#pragma unroll
            for (int j = 0; j < 4; ++j) acc[h][j] = 0.f;
#pragma unroll
        for (int j = 0; j < 4; ++j) {
            const uint32_t w[4] = {kv[j].x, kv[j].y, kv[j].z, kv[j].w};
#pragma unroll
            for (int e = 0; e < 4; ++e) {
                const float lo = bf16lo(w[e]), hi = bf16hi(w[e]);
#pragma unroll
                for (int h = 0; h < NH; ++h) {
                    acc[h][j] = fmaf(q[h][2 * e], lo, acc[h][j]);
                    acc[h][j] = fmaf(q[h][2 * e + 1], hi, acc[h][j]);
                }
            }
        }
        __syncwarp();
        if (lane == 0) mbar_arrive(smem_u32(&ms->empty[ring.stage]));
        ring_advance(ring);
        __nv_bfloat16* so = g_scores + ((NH == 2) ? g * 64 : kScoreElemsA + (g - kTilesA) * 32) + warp * 4 + row;
#pragma unroll
        for (int h = 0; h < NH; ++h) {
            const float dot = reduce4(acc[h][0], acc[h][1], acc[h][2], acc[h][3], lane);
            const __nv_bfloat16 sb = __float2bfloat16_rn(bf16round(dot) * 0.0625f);
            mx[h] = fmaxf(mx[h], __bfloat162float(sb));
            if ((lane & 7) == 0) so[h * 32] = sb;
        }
        mbar_wait(smem_u32(&ms->full[ring.stage]), ring.phase);
        g = lds_i32(&ms->slot_g[ring.stage]);
    } while (g >= 0 && (g >> 10) == tag);
#pragma unroll
    for (int h = 0; h < NH; ++h) {
        float m = mx[h];
        m = fmaxf(m, __shfl_xor_sync(0xffffffffu, m, 16));
        m = fmaxf(m, __shfl_xor_sync(0xffffffffu, m, 8));
        if (lane == 0) ms->wmax[qh0 + h][warp] = m;
    }
}

template <int NH>
__device__ __forceinline__ void v_run(int& g, Ring& ring, const char* smem_ring,
                                      float* mbuf, Misc* ms, int warp, int lane, int cta, int G) {
    const int tag = g >> 10;
    const int qh0 = (NH == 2) ? tag * 2 : kQH + (tag - kKvhA);
    float ml2[NH];
#pragma unroll
    for (int h = 0; h < NH; ++h) ml2[h] = ms->gmax2[qh0 + h];
    float acc[NH][8], l[NH];
#pragma unroll
    for (int h = 0; h < NH; ++h) {
        l[h] = 0.f;
#pragma unroll
        for (int d = 0; d < 8; ++d) acc[h][d] = 0.f;
    }
    do {
        const char* slot = smem_ring + ring.stage * kStageBytes;
        const uint4* vt = reinterpret_cast<const uint4*>(slot) + (warp * 4) * 32 + lane;
        uint4 vv[4];
#pragma unroll
        for (int j = 0; j < 4; ++j) vv[j] = vt[j * 32];
        float p[NH][4];
#pragma unroll
        for (int h = 0; h < NH; ++h) {
            const uint2 s2 = *reinterpret_cast<const uint2*>(slot + kTileBytes + (h * 32 + warp * 4) * 2);
            p[h][0] = ex2(fmaf(bf16lo(s2.x), kLog2e, -ml2[h]));
            p[h][1] = ex2(fmaf(bf16hi(s2.x), kLog2e, -ml2[h]));
            p[h][2] = ex2(fmaf(bf16lo(s2.y), kLog2e, -ml2[h]));
            p[h][3] = ex2(fmaf(bf16hi(s2.y), kLog2e, -ml2[h]));
            l[h] += (p[h][0] + p[h][1]) + (p[h][2] + p[h][3]);
        }
#pragma unroll
        for (int j = 0; j < 4; ++j) {
            const uint32_t w[4] = {vv[j].x, vv[j].y, vv[j].z, vv[j].w};
#pragma unroll
            for (int e = 0; e < 4; ++e) {
                const float lo = bf16lo(w[e]), hi = bf16hi(w[e]);
#pragma unroll
                for (int h = 0; h < NH; ++h) {
                    acc[h][2 * e]     = fmaf(p[h][j], lo, acc[h][2 * e]);
                    acc[h][2 * e + 1] = fmaf(p[h][j], hi, acc[h][2 * e + 1]);
                }
            }
        }
        __syncwarp();
        if (lane == 0) mbar_arrive(smem_u32(&ms->empty[ring.stage]));
        ring_advance(ring);
        mbar_wait(smem_u32(&ms->full[ring.stage]), ring.phase);
        g = lds_i32(&ms->slot_g[ring.stage]);
    } while (g >= 0 && (g >> 10) == tag);

    const int t = warp * 32 + lane;
#pragma unroll
    for (int h = 0; h < NH; ++h) {
        float4* mb = reinterpret_cast<float4*>(mbuf + (warp * 2 + h) * kDh + lane * 8);
        mb[0] = make_float4(acc[h][0], acc[h][1], acc[h][2], acc[h][3]);
        mb[1] = make_float4(acc[h][4], acc[h][5], acc[h][6], acc[h][7]);
        if (lane == 0) ms->lbuf[warp * 2 + h] = l[h];
    }
    consumer_sync();
#pragma unroll
    for (int h = 0; h < NH; ++h) {
        float s = 0.f;
#pragma unroll
        for (int w = 0; w < kNCW; ++w) s += mbuf[(w * 2 + h) * kDh + t];
        g_po[((size_t)(qh0 + h) * G + cta) * kDh + t] = s;
        if (t == h) {
            float ls = 0.f;
#pragma unroll
            for (int w = 0; w < kNCW; ++w) ls += ms->lbuf[w * 2 + h];
            ms->l[qh0 + h] = ls;
        }
    }
    consumer_sync();
}

__global__ void __launch_bounds__(kThreads, 1)
attn_decode_kernel(const Params P) {
    extern __shared__ __align__(1024) char smem[];
    char*  smem_ring  = smem + kOffRing;
    char*  wo_s       = smem + kOffWo;
    __nv_bfloat16* qs = reinterpret_cast<__nv_bfloat16*>(smem + kOffQ);
    float* mbuf       = reinterpret_cast<float*>(smem + kOffQ);
    Misc*  ms         = reinterpret_cast<Misc*>(smem + kOffMisc);

    const int tid = threadIdx.x, warp = tid >> 5, lane = tid & 31;
    const int G = gridDim.x, c = blockIdx.x;

    if (tid == 0) {
        for (int s = 0; s < kStages; ++s) {
            mbar_init(smem_u32(&ms->full[s]), 1);
            mbar_init(smem_u32(&ms->empty[s]), kNCW);
        }
        mbar_init(smem_u32(&ms->wobar), 1);
        mbar_init(smem_u32(&ms->qbar), kNCW);
        mbar_init(smem_u32(&ms->sbar), 1);
        asm volatile("fence.mbarrier_init.release.cluster;" ::: "memory");
        unsigned long long v;
        asm volatile("ld.acquire.gpu.global.u64 %0, [%1];" : "=l"(v) : "l"(&g_bar) : "memory");
        const unsigned long long per = (unsigned long long)kNumGridBars * G;
        ms->bar_base = (v / per) * per;
    }
    for (int i = tid; i < 2 * kQH; i += kThreads) ms->l[i] = 0.f;
    for (int i = tid; i < 2 * kQH * kNCW; i += kThreads) (&ms->wmax[0][0])[i] = -INFINITY;
    __syncthreads();

    if (warp == kNCW) {
        if (lane == 0) {
            Ring r{0, 1};
            uint64_t pol = 0;
            asm volatile("createpolicy.fractional.L2::evict_first.b64 %0, 1.0;" : "=l"(pol));
            int issued = 0;

            bool wo_issued = (c >= kNumSlices);
            bool qwaited = false;
            unsigned nxt = atomicAdd(&g_tile_ctr[0], (unsigned)kBatch);
            while (nxt < (unsigned)kTiles) {
                if (!qwaited) {
                    mbar_wait(smem_u32(&ms->qbar), 0);
                    qwaited = true;
                }
                const unsigned g0 = nxt;
                nxt = atomicAdd(&g_tile_ctr[0], (unsigned)kBatch);
#pragma unroll
                for (int b = 0; b < kBatch; ++b) {
                    const int g = (int)g0 + b;
                    if (g < kTiles) {
                        const char* src = (g < kTilesA) ? reinterpret_cast<const char*>(P.kA) + (size_t)g * kTileBytes
                                                        : reinterpret_cast<const char*>(P.kB) + (size_t)(g - kTilesA) * kTileBytes;
                        mbar_wait(smem_u32(&ms->empty[r.stage]), r.phase);
                        ms->slot_g[r.stage] = g;
                        mbar_expect_tx(smem_u32(&ms->full[r.stage]), kTileBytes);
                        bulk_g2s_stream(smem_u32(smem_ring + r.stage * kStageBytes), src, kTileBytes, smem_u32(&ms->full[r.stage]), pol);
                        ring_advance(r);
                        ++issued;
                    }
                }
                if (!wo_issued && issued >= 16) {
                    const __nv_bfloat16* wo = (c < kNumSlices / 2 ? P.woA : P.woB)
                                              + (size_t)(c % (kNumSlices / 2)) * kSliceRows * kD;
                    mbar_expect_tx(smem_u32(&ms->wobar), kSliceRows * kD * 2);
                    bulk_g2s(smem_u32(wo_s), wo, kSliceRows * kD * 2, smem_u32(&ms->wobar));
                    wo_issued = true;
                }
            }
            if (!wo_issued) {
                const __nv_bfloat16* wo = (c < kNumSlices / 2 ? P.woA : P.woB)
                                          + (size_t)(c % (kNumSlices / 2)) * kSliceRows * kD;
                mbar_expect_tx(smem_u32(&ms->wobar), kSliceRows * kD * 2);
                bulk_g2s(smem_u32(wo_s), wo, kSliceRows * kD * 2, smem_u32(&ms->wobar));
            }
            mbar_wait(smem_u32(&ms->empty[r.stage]), r.phase);
            ms->slot_g[r.stage] = -1;
            mbar_arrive(smem_u32(&ms->full[r.stage]));
            ring_advance(r);

            bool ready = false;
            int npend = 0, pend_stage[kStages], pend_g[kStages];
            auto issue_scores = [&](int stage, int g) {
                const __nv_bfloat16* ssrc = g_scores + ((g < kTilesA) ? g * 64 : kScoreElemsA + (g - kTilesA) * 32);
                bulk_g2s(smem_u32(smem_ring + stage * kStageBytes + kTileBytes), ssrc,
                         (g < kTilesA) ? 128u : 64u, smem_u32(&ms->full[stage]));
            };
            auto flush_pending = [&]() {
                asm volatile("fence.proxy.async;" ::: "memory");
                for (int k = 0; k < npend; ++k) issue_scores(pend_stage[k], pend_g[k]);
                npend = 0;
            };
            nxt = atomicAdd(&g_tile_ctr[1], (unsigned)kBatch);
            while (nxt < (unsigned)kTiles) {
                const unsigned g0 = nxt;
                nxt = atomicAdd(&g_tile_ctr[1], (unsigned)kBatch);
#pragma unroll
                for (int b = 0; b < kBatch; ++b) {
                    const int g = (int)g0 + b;
                    if (g < kTiles) {
                        if (!ready && !mbar_try_wait(smem_u32(&ms->empty[r.stage]), r.phase)) {
                            mbar_wait(smem_u32(&ms->sbar), 0);
                            ready = true;
                            flush_pending();
                        }
                        const char* src = (g < kTilesA) ? reinterpret_cast<const char*>(P.vA) + (size_t)g * kTileBytes
                                                        : reinterpret_cast<const char*>(P.vB) + (size_t)(g - kTilesA) * kTileBytes;
                        mbar_wait(smem_u32(&ms->empty[r.stage]), r.phase);
                        ms->slot_g[r.stage] = g;
                        mbar_expect_tx(smem_u32(&ms->full[r.stage]), kTileBytes + ((g < kTilesA) ? 128u : 64u));
                        bulk_g2s_stream(smem_u32(smem_ring + r.stage * kStageBytes), src, kTileBytes, smem_u32(&ms->full[r.stage]), pol);
                        if (!ready && mbar_try_wait(smem_u32(&ms->sbar), 0)) { ready = true; flush_pending(); }
                        if (ready) issue_scores(r.stage, g);
                        else { pend_stage[npend] = r.stage; pend_g[npend] = g; ++npend; }
                        ring_advance(r);
                    }
                }
            }
            if (!ready) { mbar_wait(smem_u32(&ms->sbar), 0); ready = true; flush_pending(); }
            mbar_wait(smem_u32(&ms->empty[r.stage]), r.phase);
            ms->slot_g[r.stage] = -1;
            mbar_arrive(smem_u32(&ms->full[r.stage]));
        }
        return;
    }

    const unsigned long long bar_base = ms->bar_base;
    STAMP(0);

    {
        float* qred = &ms->red[0][0];
        bool signalled = false;
        for (int blk = c; blk < 2 * kHD / 64; blk += G) {
            const int part = blk / (kHD / 64);
            const int n0 = (blk % (kHD / 64)) * 64;
            const __nv_bfloat16* x  = part ? P.xB : P.xA;
            const __nv_bfloat16* wq = part ? P.wqB : P.wqA;
            const int chunk = tid & 7, krow = tid >> 3;
            float a[8];
#pragma unroll
            for (int e = 0; e < 8; ++e) a[e] = 0.f;
#pragma unroll
            for (int it = 0; it < kD / 32; ++it) {
                const int k = krow + it * 32;
                const uint4 w = __ldg(reinterpret_cast<const uint4*>(wq + (size_t)k * kHD + n0 + chunk * 8));
                const float xv = __bfloat162float(x[k]);
                a[0] = fmaf(xv, bf16lo(w.x), a[0]); a[1] = fmaf(xv, bf16hi(w.x), a[1]);
                a[2] = fmaf(xv, bf16lo(w.y), a[2]); a[3] = fmaf(xv, bf16hi(w.y), a[3]);
                a[4] = fmaf(xv, bf16lo(w.z), a[4]); a[5] = fmaf(xv, bf16hi(w.z), a[5]);
                a[6] = fmaf(xv, bf16lo(w.w), a[6]); a[7] = fmaf(xv, bf16hi(w.w), a[7]);
            }
            if (blk + G >= 2 * kHD / 64) {
                __syncwarp();
                if (lane == 0) mbar_arrive(smem_u32(&ms->qbar));
                signalled = true;
            }
#pragma unroll
            for (int e = 0; e < 8; ++e) {
                a[e] += __shfl_xor_sync(0xffffffffu, a[e], 8);
                a[e] += __shfl_xor_sync(0xffffffffu, a[e], 16);
            }
            if (lane < 8) {
#pragma unroll
                for (int e = 0; e < 8; ++e) qred[warp * 64 + lane * 8 + e] = a[e];
            }
            consumer_sync();
            if (tid < 64) {
                float s = 0.f;
#pragma unroll
                for (int w = 0; w < kNCW; ++w) s += qred[w * 64 + tid];
                g_q[part * kHD + n0 + tid] = __float2bfloat16_rn(s);
            }
            consumer_sync();
        }
        if (!signalled) {
            __syncwarp();
            if (lane == 0) mbar_arrive(smem_u32(&ms->qbar));
        }
    }
    if (c == 0 && tid < 2 * kQH) g_gmax[tid] = 0u;
    consumer_sync();
    STAMP(1);
    if (tid == 0) grid_arrive_wait(bar_base + 1ULL * G);
    consumer_sync();
    STAMP(2);
    for (int i = tid; i < 2 * kHD / 8; i += kNCT)
        reinterpret_cast<uint4*>(qs)[i] = __ldcg(reinterpret_cast<const uint4*>(g_q) + i);
    consumer_sync();

    Ring ring{0, 0};
    mbar_wait(smem_u32(&ms->full[ring.stage]), ring.phase);
    int g = lds_i32(&ms->slot_g[ring.stage]);
    while (g >= 0) {
        if (g < kTilesA) k_run<2>(g, ring, smem_ring, qs, ms, warp, lane);
        else             k_run<1>(g, ring, smem_ring, qs, ms, warp, lane);
    }
    __syncwarp();
    if (lane == 0) mbar_arrive(smem_u32(&ms->empty[ring.stage]));
    ring_advance(ring);
    asm volatile("fence.proxy.async;" ::: "memory");
    consumer_sync();
    if (tid < 2 * kQH) {
        float m = -INFINITY;
#pragma unroll
        for (int w = 0; w < kNCW; ++w) m = fmaxf(m, ms->wmax[tid][w]);
        if (m > -INFINITY) atomicMax(&g_gmax[tid], enc_f(m));
    }
    consumer_sync();
    STAMP(3);
    if (tid == 0) {
        grid_arrive_wait(bar_base + 2ULL * G);
        mbar_arrive(smem_u32(&ms->sbar));
    }
    consumer_sync();
    if (tid < 2 * kQH) ms->gmax2[tid] = dec_f(__ldcg(&g_gmax[tid])) * kLog2e;
    consumer_sync();

    mbar_wait(smem_u32(&ms->full[ring.stage]), ring.phase);
    g = lds_i32(&ms->slot_g[ring.stage]);
    while (g >= 0) {
        if (g < kTilesA) v_run<2>(g, ring, smem_ring, mbuf, ms, warp, lane, c, G);
        else             v_run<1>(g, ring, smem_ring, mbuf, ms, warp, lane, c, G);
    }
    if (tid < 2 * kQH) g_l[tid * G + c] = ms->l[tid];
    consumer_sync();
    STAMP(4);
    if (tid == 0) grid_arrive_wait(bar_base + 3ULL * G);
    consumer_sync();
    STAMP(5);
    if (c == 0 && tid < 2) g_tile_ctr[tid] = 0u;

    for (int sl = c; sl < kNumSlices; sl += G) {
        const int part = sl / (kNumSlices / 2);
        const int r0 = (sl % (kNumSlices / 2)) * kSliceRows;
        const int head = part * kQH + r0 / kDh, d0 = r0 % kDh;
        const int j4 = tid & 15, cg = tid >> 4;
        constexpr int kIt = (kMaxGrid + 15) / 16;
        float4 pv[kIt];
        float lv[kIt];
#pragma unroll
        for (int it = 0; it < kIt; ++it) {
            const int cc = cg + it * 16;
            lv[it] = (cc < G) ? __ldcg(&g_l[head * G + cc]) : 0.f;
            pv[it] = (cc < G) ? __ldcg(reinterpret_cast<const float4*>(&g_po[((size_t)head * G + cc) * kDh + d0 + 4 * j4]))
                              : make_float4(0.f, 0.f, 0.f, 0.f);
        }
        float4 acc4 = make_float4(0.f, 0.f, 0.f, 0.f);
        float lsum = 0.f;
#pragma unroll
        for (int it = 0; it < kIt; ++it) {
            if (lv[it] > 0.f) {
                acc4.x += pv[it].x; acc4.y += pv[it].y; acc4.z += pv[it].z; acc4.w += pv[it].w;
                lsum += lv[it];
            }
        }
        acc4.x += __shfl_xor_sync(0xffffffffu, acc4.x, 16);
        acc4.y += __shfl_xor_sync(0xffffffffu, acc4.y, 16);
        acc4.z += __shfl_xor_sync(0xffffffffu, acc4.z, 16);
        acc4.w += __shfl_xor_sync(0xffffffffu, acc4.w, 16);
        lsum   += __shfl_xor_sync(0xffffffffu, lsum, 16);
        if (lane < 16) *reinterpret_cast<float4*>(&ms->red[warp][4 * j4]) = acc4;
        if (lane == 0) ms->lbuf[warp] = lsum;
        STAMP(9);
        consumer_sync();
        if (tid < kSliceRows) {
            float tot = 0.f, lt = 0.f;
#pragma unroll
            for (int w = 0; w < kNCW; ++w) { tot += ms->red[w][tid]; lt += ms->lbuf[w]; }
            ms->os[tid] = bf16round(tot / lt);
        }
        consumer_sync();
        STAMP(10);
        const bool from_smem = (sl == c);
        if (from_smem) mbar_wait(smem_u32(&ms->wobar), 0);
        if (tid < kD / 2) {
            const __nv_bfloat16* wo_g = (part ? P.woB : P.woA) + (size_t)r0 * kD;
            const uint32_t* w2 = (from_smem ? reinterpret_cast<const uint32_t*>(wo_s)
                                            : reinterpret_cast<const uint32_t*>(wo_g)) + tid;
            float a0 = 0.f, a1 = 0.f, b0 = 0.f, b1 = 0.f;
#pragma unroll
            for (int r4 = 0; r4 < kSliceRows / 4; ++r4) {
                const float4 o4 = *reinterpret_cast<const float4*>(&ms->os[4 * r4]);
                const uint32_t w0 = w2[(4 * r4 + 0) * (kD / 2)], w1 = w2[(4 * r4 + 1) * (kD / 2)];
                const uint32_t w2_ = w2[(4 * r4 + 2) * (kD / 2)], w3 = w2[(4 * r4 + 3) * (kD / 2)];
                a0 = fmaf(o4.x, bf16lo(w0), a0);  a1 = fmaf(o4.x, bf16hi(w0), a1);
                b0 = fmaf(o4.y, bf16lo(w1), b0);  b1 = fmaf(o4.y, bf16hi(w1), b1);
                a0 = fmaf(o4.z, bf16lo(w2_), a0); a1 = fmaf(o4.z, bf16hi(w2_), a1);
                b0 = fmaf(o4.w, bf16lo(w3), b0);  b1 = fmaf(o4.w, bf16hi(w3), b1);
            }
            a0 += b0; a1 += b1;
            *reinterpret_cast<float2*>(&g_outp[sl * kD + 2 * tid]) = make_float2(a0, a1);
        }
        consumer_sync();
    }
    STAMP(6);
    if (tid == 0) grid_arrive_wait(bar_base + 4ULL * G);
    consumer_sync();
    STAMP(7);

    for (int blk = c; blk < 2 * kD / 64; blk += G) {
        const int j = blk * 64 + (tid & 63), grp = tid >> 6;
        const int pj = j / kD, col = j - pj * kD;
        float s = 0.f;
#pragma unroll
        for (int it = 0; it < kNumSlices / 2 / 4; ++it)
            s += __ldcg(&g_outp[(pj * (kNumSlices / 2) + grp * (kNumSlices / 2 / 4) + it) * kD + col]);
        ms->red[grp][tid & 63] = s;
        consumer_sync();
        if (tid < 64) {
            const float tot = (ms->red[0][tid] + ms->red[1][tid]) + (ms->red[2][tid] + ms->red[3][tid]);
            P.out[blk * 64 + tid] = __float2bfloat16_rn(tot);
        }
        consumer_sync();
    }
    STAMP(8);
}

}

extern "C" void kernel_launch(void* const* d_in, const int* in_sizes, int n_in,
                              void* d_out, int out_size) {
    (void)in_sizes; (void)n_in; (void)out_size;
    Params P;
    P.xA  = (const __nv_bfloat16*)d_in[0];
    P.kA  = (const __nv_bfloat16*)d_in[1];
    P.vA  = (const __nv_bfloat16*)d_in[2];
    P.wqA = (const __nv_bfloat16*)d_in[3];
    P.woA = (const __nv_bfloat16*)d_in[4];
    P.xB  = (const __nv_bfloat16*)d_in[5];
    P.kB  = (const __nv_bfloat16*)d_in[6];
    P.vB  = (const __nv_bfloat16*)d_in[7];
    P.wqB = (const __nv_bfloat16*)d_in[8];
    P.woB = (const __nv_bfloat16*)d_in[9];
    P.out = (__nv_bfloat16*)d_out;

    int dev = 0, sms = 0;
    cudaGetDevice(&dev);
    cudaDeviceGetAttribute(&sms, cudaDevAttrMultiProcessorCount, dev);
    const int G = sms < kMaxGrid ? sms : kMaxGrid;
    cudaFuncSetAttribute(attn_decode_kernel, cudaFuncAttributeMaxDynamicSharedMemorySize, kSmemTotal);
    void* args[] = {(void*)&P};
    cudaLaunchCooperativeKernel((const void*)attn_decode_kernel, dim3(G), dim3(kThreads), args,
                                (size_t)kSmemTotal, cudaStreamPerThread);
}
```
